```python
import torch

def _softmax(x, axis=-1):
    return torch.softmax(x, dim=axis)
def _gelu(x):
    return torch.nn.functional.gelu(x, approximate="tanh")
def _silu(x):
    return torch.nn.functional.silu(x)
def _sigmoid(x):
    return torch.sigmoid(x)
def _layernorm(x, axis=-1, eps=1e-5):
    m = x.mean(dim=axis, keepdim=True)
    v = x.var(dim=axis, keepdim=True, unbiased=False)
    return (x - m) / torch.sqrt(v + eps)
def _scatter_add(tgt, idx, src, axis=0):
    return tgt.clone().index_add_(axis, idx, src)
def _segment_sum(src, seg, n):
    out = torch.zeros((n,) + src.shape[1:], dtype=src.dtype)
    return out.index_add_(0, seg, src)
def _pad(x, pw):
    flat = tuple(v for pair in reversed(pw) for v in pair)
    return torch.nn.functional.pad(x, flat)

kernel_name = 'standalone__normalfloat_lut_codebook_lookup__prompt'

def setup_inputs():

    _w = (lambda a: (lambda t: t.to(torch.bfloat16) if t.is_floating_point() else t)(torch.as_tensor(a)))
    B, S, D, F = 1, 2048, 1024, 3584
    G = -1 if -1 > 0 else D
    D = (D // G) * G
    ng = D // G
    nf4 = torch.tensor([
        -1.0, -0.6961928009986877, -0.5250730514526367, -0.39491748809814453,
        -0.28444138169288635, -0.18477343022823334, -0.09105003625154495, 0.0,
        0.07958029955625534, 0.16093020141124725, 0.24611230194568634, 0.33791524171829224,
        0.44070982933044434, 0.5626170039176941, 0.7229568362236023, 1.0
    ], dtype=float)
    qw = torch.randint(0, 16, (D, F)).to(torch.int64)
    absmax = (torch.abs((lambda *s: torch.randn(*s, dtype=torch.bfloat16) * 0.05)(ng, F)) + 0.01).to(float)
    return {
        "x": _w((lambda *s: torch.randn(*s, dtype=torch.bfloat16) * 0.05)(B, S, D)),
        "qw": _w(qw),
        "codebook": _w(nf4),
        "absmax": _w(absmax),
    }

def reference(x, qw, codebook, absmax):
    B, S, D = x.shape
    ng, F = absmax.shape
    G = D // ng
    w_nf = codebook[qw]
    s = (lambda x, n, axis: torch.repeat_interleave(x, n, dim=axis))(absmax, G, axis=0)
    w = (lambda x, dt: x.to(dt))(w_nf * s, x.dtype)
    return torch.einsum("bsd,df->bsf", x, w)
```

```cpp
#include <cuda_runtime.h>
#include <cuda_bf16.h>
#include <cuda.h>
#include <stdint.h>

constexpr int S_DIM = 2048, K_DIM = 1024, F_DIM = 3584;
constexpr int BM = 256, BN = 224, BK = 64;
constexpr int NKB = K_DIM / BK, MT = S_DIM / BM, NT = F_DIM / BN;
constexpr int NHELP = 4;
constexpr int NOWN = 13;
constexpr int KB1 = 12;
constexpr int HELPER_DELAY = 1500;

constexpr uint32_t SBASE = 1024;
constexpr int A_SLOT = 16384, B_BYTES = BN * BK * 2, RAW_BOX = 16 * BN * 4;
constexpr int OFF_B = 7 * A_SLOT, OFF_BAR = OFF_B + 4 * B_BYTES, SMEM_BYTES = OFF_BAR + 256;
constexpr uint32_t BARS = SBASE + OFF_BAR;
constexpr uint32_t BAR_A = BARS, BAR_B = BARS + 64, BAR_E = BARS + 96, BAR_F = BARS + 128, BAR_R = BARS + 136;

__device__ uint4 g_wblob[K_DIM * F_DIM / 8];
__device__ unsigned g_flags[NT * 4 * 32];
struct Scratch { uint8_t* blob; unsigned* flags; unsigned zero; };
__device__ __forceinline__ unsigned* flag_ptr(const Scratch& g, int tile, int kb) { return g.flags + (tile * 4 + (kb & 3)) * 32 + (kb >> 2); }

__device__ __forceinline__ void mbar_init(uint32_t bar, uint32_t cnt) { asm volatile("mbarrier.init.shared::cta.b64 [%0], %1;" ::"r"(bar), "r"(cnt) : "memory"); }
__device__ __forceinline__ void mbar_init_fence() { asm volatile("fence.mbarrier_init.release.cluster;" ::: "memory"); }
__device__ __forceinline__ void mbar_wait(uint32_t bar, uint32_t parity) {
    asm volatile("{\n.reg .pred p;\n.reg .u32 c;\nmov.u32 c, 0;\n"
                 "WL:\nmbarrier.try_wait.parity.shared::cta.b64 p, [%0], %1;\n@p bra WD;\n"
                 "add.u32 c, c, 1;\nsetp.lt.u32 p, c, 0x40000;\n@p bra WL;\ntrap;\nWD:\n}" ::"r"(bar), "r"(parity) : "memory");
}
__device__ __forceinline__ void mbar_wait2(uint32_t bar0, uint32_t par0, uint32_t bar1, uint32_t par1) {
    asm volatile("{\n.reg .pred p, q;\n.reg .u32 c;\nmov.u32 c, 0;\nWL:\n"
                 "mbarrier.try_wait.parity.shared::cta.b64 p, [%0], %1;\nmbarrier.try_wait.parity.shared::cta.b64 q, [%2], %3;\n"
                 "and.pred p, p, q;\n@p bra WD;\n"
                 "add.u32 c, c, 1;\nsetp.lt.u32 p, c, 0x40000;\n@p bra WL;\ntrap;\nWD:\n}" ::"r"(bar0), "r"(par0), "r"(bar1), "r"(par1) : "memory");
}
template <int ID, int N> __device__ __forceinline__ void bar_sync() { asm volatile("bar.sync %0, %1;" ::"n"(ID), "n"(N) : "memory"); }
template <int ID, int N> __device__ __forceinline__ void bar_arrive() { asm volatile("bar.arrive %0, %1;" ::"n"(ID), "n"(N) : "memory"); }
__device__ __forceinline__ void fence_async_smem() { asm volatile("fence.proxy.async.shared::cta;" ::: "memory"); }
__device__ __forceinline__ void wg_fence() { asm volatile("wgmma.fence.sync.aligned;" ::: "memory"); }
__device__ __forceinline__ void wg_commit() { asm volatile("wgmma.commit_group.sync.aligned;" ::: "memory"); }
template <int N> __device__ __forceinline__ void wg_wait() { asm volatile("wgmma.wait_group.sync.aligned %0;" ::"n"(N) : "memory"); }
template <int N> __device__ __forceinline__ void fence_acc(float (&a)[N]) {
#pragma unroll
    for (int i = 0; i < N; i++) asm volatile("" : "+f"(a[i])::"memory");
}
__device__ __forceinline__ uint32_t pack_bf16(float lo, float hi) { uint32_t r; asm("cvt.rn.bf16x2.f32 %0, %1, %2;" : "=r"(r) : "f"(hi), "f"(lo)); return r; }
__device__ __forceinline__ uint32_t mul_bf16x2(uint32_t a, uint32_t b) { uint32_t r; asm("mul.rn.bf16x2 %0, %1, %2;" : "=r"(r) : "r"(a), "r"(b)); return r; }
__device__ __forceinline__ uint32_t prmt(uint32_t a, uint32_t b, uint32_t s) { uint32_t r; asm("prmt.b32 %0, %1, %2, %3;" : "=r"(r) : "r"(a), "r"(b), "r"(s)); return r; }
__device__ __forceinline__ int ld_code(const int* p) { int v; asm volatile("ld.global.L1::no_allocate.b32 %0, [%1];" : "=r"(v) : "l"(p) : "memory"); return v; }
__device__ __forceinline__ uint32_t ld_u16(const void* p) { uint16_t v; asm volatile("ld.global.u16 %0, [%1];" : "=h"(v) : "l"(p) : "memory"); return v; }
__device__ __forceinline__ unsigned ld_relaxed(const unsigned* p) { unsigned v; asm volatile("ld.relaxed.gpu.global.u32 %0, [%1];" : "=r"(v) : "l"(p) : "memory"); return v; }
__device__ __forceinline__ int lds32(uint32_t a) { int v; asm volatile("ld.shared.b32 %0, [%1];" : "=r"(v) : "r"(a) : "memory"); return v; }
__device__ __forceinline__ void sts128(uint32_t a, uint4 v) { asm volatile("st.shared.v4.b32 [%0], {%1, %2, %3, %4};" ::"r"(a), "r"(v.x), "r"(v.y), "r"(v.z), "r"(v.w) : "memory"); }

__device__ __forceinline__ void wgmma_m64n224k16(float (&d)[112], uint64_t da, uint64_t db, int scale_d) {
    asm volatile(
        "{\n.reg .pred p;\nsetp.ne.b32 p, %114, 0;\n"
        "wgmma.mma_async.sync.aligned.m64n224k16.f32.bf16.bf16 "
        "{%0, %1, %2, %3, %4, %5, %6, %7, %8, %9, %10, %11, %12, %13, %14, %15, "
        "%16, %17, %18, %19, %20, %21, %22, %23, %24, %25, %26, %27, %28, %29, %30, %31, "
        "%32, %33, %34, %35, %36, %37, %38, %39, %40, %41, %42, %43, %44, %45, %46, %47, "
        "%48, %49, %50, %51, %52, %53, %54, %55, %56, %57, %58, %59, %60, %61, %62, %63, "
        "%64, %65, %66, %67, %68, %69, %70, %71, %72, %73, %74, %75, %76, %77, %78, %79, "
        "%80, %81, %82, %83, %84, %85, %86, %87, %88, %89, %90, %91, %92, %93, %94, %95, "
        "%96, %97, %98, %99, %100, %101, %102, %103, %104, %105, %106, %107, %108, %109, %110, %111}, "
        "%112, %113, p, 1, 1, 0, 0;\n}\n"
        : "+f"(d[0]), "+f"(d[1]), "+f"(d[2]), "+f"(d[3]), "+f"(d[4]), "+f"(d[5]), "+f"(d[6]), "+f"(d[7]),
          "+f"(d[8]), "+f"(d[9]), "+f"(d[10]), "+f"(d[11]), "+f"(d[12]), "+f"(d[13]), "+f"(d[14]), "+f"(d[15]),
          "+f"(d[16]), "+f"(d[17]), "+f"(d[18]), "+f"(d[19]), "+f"(d[20]), "+f"(d[21]), "+f"(d[22]), "+f"(d[23]),
          "+f"(d[24]), "+f"(d[25]), "+f"(d[26]), "+f"(d[27]), "+f"(d[28]), "+f"(d[29]), "+f"(d[30]), "+f"(d[31]),
          "+f"(d[32]), "+f"(d[33]), "+f"(d[34]), "+f"(d[35]), "+f"(d[36]), "+f"(d[37]), "+f"(d[38]), "+f"(d[39]),
          "+f"(d[40]), "+f"(d[41]), "+f"(d[42]), "+f"(d[43]), "+f"(d[44]), "+f"(d[45]), "+f"(d[46]), "+f"(d[47]),
          "+f"(d[48]), "+f"(d[49]), "+f"(d[50]), "+f"(d[51]), "+f"(d[52]), "+f"(d[53]), "+f"(d[54]), "+f"(d[55]),
          "+f"(d[56]), "+f"(d[57]), "+f"(d[58]), "+f"(d[59]), "+f"(d[60]), "+f"(d[61]), "+f"(d[62]), "+f"(d[63]),
          "+f"(d[64]), "+f"(d[65]), "+f"(d[66]), "+f"(d[67]), "+f"(d[68]), "+f"(d[69]), "+f"(d[70]), "+f"(d[71]),
          "+f"(d[72]), "+f"(d[73]), "+f"(d[74]), "+f"(d[75]), "+f"(d[76]), "+f"(d[77]), "+f"(d[78]), "+f"(d[79]),
          "+f"(d[80]), "+f"(d[81]), "+f"(d[82]), "+f"(d[83]), "+f"(d[84]), "+f"(d[85]), "+f"(d[86]), "+f"(d[87]),
          "+f"(d[88]), "+f"(d[89]), "+f"(d[90]), "+f"(d[91]), "+f"(d[92]), "+f"(d[93]), "+f"(d[94]), "+f"(d[95]),
          "+f"(d[96]), "+f"(d[97]), "+f"(d[98]), "+f"(d[99]), "+f"(d[100]), "+f"(d[101]), "+f"(d[102]), "+f"(d[103]),
          "+f"(d[104]), "+f"(d[105]), "+f"(d[106]), "+f"(d[107]), "+f"(d[108]), "+f"(d[109]), "+f"(d[110]), "+f"(d[111])
        : "l"(da), "l"(db), "r"(scale_d));
}
__device__ __forceinline__ void wgmma_rs_n128(float (&d)[64], const uint32_t* a, uint64_t db) {
    asm volatile(
        "wgmma.mma_async.sync.aligned.m64n128k16.f32.bf16.bf16 "
        "{%0, %1, %2, %3, %4, %5, %6, %7, %8, %9, %10, %11, %12, %13, %14, %15, "
        "%16, %17, %18, %19, %20, %21, %22, %23, %24, %25, %26, %27, %28, %29, %30, %31, "
        "%32, %33, %34, %35, %36, %37, %38, %39, %40, %41, %42, %43, %44, %45, %46, %47, "
        "%48, %49, %50, %51, %52, %53, %54, %55, %56, %57, %58, %59, %60, %61, %62, %63}, "
        "{%64, %65, %66, %67}, %68, 1, 1, 1, 0;\n"
        : "+f"(d[0]), "+f"(d[1]), "+f"(d[2]), "+f"(d[3]), "+f"(d[4]), "+f"(d[5]), "+f"(d[6]), "+f"(d[7]),
          "+f"(d[8]), "+f"(d[9]), "+f"(d[10]), "+f"(d[11]), "+f"(d[12]), "+f"(d[13]), "+f"(d[14]), "+f"(d[15]),
          "+f"(d[16]), "+f"(d[17]), "+f"(d[18]), "+f"(d[19]), "+f"(d[20]), "+f"(d[21]), "+f"(d[22]), "+f"(d[23]),
          "+f"(d[24]), "+f"(d[25]), "+f"(d[26]), "+f"(d[27]), "+f"(d[28]), "+f"(d[29]), "+f"(d[30]), "+f"(d[31]),
          "+f"(d[32]), "+f"(d[33]), "+f"(d[34]), "+f"(d[35]), "+f"(d[36]), "+f"(d[37]), "+f"(d[38]), "+f"(d[39]),
          "+f"(d[40]), "+f"(d[41]), "+f"(d[42]), "+f"(d[43]), "+f"(d[44]), "+f"(d[45]), "+f"(d[46]), "+f"(d[47]),
          "+f"(d[48]), "+f"(d[49]), "+f"(d[50]), "+f"(d[51]), "+f"(d[52]), "+f"(d[53]), "+f"(d[54]), "+f"(d[55]),
          "+f"(d[56]), "+f"(d[57]), "+f"(d[58]), "+f"(d[59]), "+f"(d[60]), "+f"(d[61]), "+f"(d[62]), "+f"(d[63])
        : "r"(a[0]), "r"(a[1]), "r"(a[2]), "r"(a[3]), "l"(db));
}
__device__ __forceinline__ void wgmma_rs_n96(float (&d)[48], const uint32_t* a, uint64_t db) {
    asm volatile(
        "wgmma.mma_async.sync.aligned.m64n96k16.f32.bf16.bf16 "
        "{%0, %1, %2, %3, %4, %5, %6, %7, %8, %9, %10, %11, %12, %13, %14, %15, "
        "%16, %17, %18, %19, %20, %21, %22, %23, %24, %25, %26, %27, %28, %29, %30, %31, "
        "%32, %33, %34, %35, %36, %37, %38, %39, %40, %41, %42, %43, %44, %45, %46, %47}, "
        "{%48, %49, %50, %51}, %52, 1, 1, 1, 0;\n"
        : "+f"(d[0]), "+f"(d[1]), "+f"(d[2]), "+f"(d[3]), "+f"(d[4]), "+f"(d[5]), "+f"(d[6]), "+f"(d[7]),
          "+f"(d[8]), "+f"(d[9]), "+f"(d[10]), "+f"(d[11]), "+f"(d[12]), "+f"(d[13]), "+f"(d[14]), "+f"(d[15]),
          "+f"(d[16]), "+f"(d[17]), "+f"(d[18]), "+f"(d[19]), "+f"(d[20]), "+f"(d[21]), "+f"(d[22]), "+f"(d[23]),
          "+f"(d[24]), "+f"(d[25]), "+f"(d[26]), "+f"(d[27]), "+f"(d[28]), "+f"(d[29]), "+f"(d[30]), "+f"(d[31]),
          "+f"(d[32]), "+f"(d[33]), "+f"(d[34]), "+f"(d[35]), "+f"(d[36]), "+f"(d[37]), "+f"(d[38]), "+f"(d[39]),
          "+f"(d[40]), "+f"(d[41]), "+f"(d[42]), "+f"(d[43]), "+f"(d[44]), "+f"(d[45]), "+f"(d[46]), "+f"(d[47])
        : "r"(a[0]), "r"(a[1]), "r"(a[2]), "r"(a[3]), "l"(db));
}
constexpr uint32_t DESC_A = (1u << 16) + (SBASE >> 4), DESC_B = (uint32_t(BN) << 16) + ((SBASE + OFF_B) >> 4);
__device__ __forceinline__ uint64_t desc_a(uint32_t lo) { uint64_t d; asm("mov.b64 %0, {%1, %2};" : "=l"(d) : "r"(lo), "n"(0x40000040)); return d; }
__device__ __forceinline__ uint64_t desc_b(uint32_t lo) { uint64_t d; asm("mov.b64 %0, {%1, %2};" : "=l"(d) : "r"(lo), "n"(8)); return d; }
__device__ __forceinline__ void mma(float (&d)[112], uint32_t a_lo, uint32_t b_lo, int scale_d) { wgmma_m64n224k16(d, desc_a(a_lo), desc_b(b_lo), scale_d); }

__device__ __forceinline__ void arrive_one(uint32_t bar) {
    asm volatile("{\n.reg .pred p;\nelect.sync _|p, 0xffffffff;\n@p mbarrier.arrive.shared::cta.b64 _, [%0];\n}" ::"r"(bar) : "memory");
}
__device__ __forceinline__ void fill_a(const CUtensorMap* tmx, int slot, int k0, int r0, int k1, int r1) {
    asm volatile("{\n.reg .pred p;\nelect.sync _|p, 0xffffffff;\n"
                 "@p mbarrier.arrive.expect_tx.shared::cta.b64 _, [%2], 16384;\n"
                 "@p cp.async.bulk.tensor.2d.shared::cluster.global.mbarrier::complete_tx::bytes [%0], [%3, {%4, %5}], [%2];\n"
                 "@p cp.async.bulk.tensor.2d.shared::cluster.global.mbarrier::complete_tx::bytes [%1], [%3, {%6, %7}], [%2];\n}"
                 ::"r"(SBASE + slot * A_SLOT), "r"(SBASE + slot * A_SLOT + 8192), "r"(BAR_A + slot * 8),
                   "l"(tmx), "r"(k0), "r"(r0), "r"(k1), "r"(r1) : "memory");
}
__device__ __forceinline__ void fill_b(const Scratch& g, int kb) {
    asm volatile("{\n.reg .pred p;\nelect.sync _|p, 0xffffffff;\n"
                 "fence.proxy.async.global;\n"
                 "@p mbarrier.arrive.expect_tx.shared::cta.b64 _, [%1], 28672;\n"
                 "@p cp.async.bulk.shared::cluster.global.mbarrier::complete_tx::bytes [%0], [%2], 28672, [%1];\n}"
                 ::"r"(SBASE + OFF_B + (kb & 3) * B_BYTES), "r"(BAR_B + (kb & 3) * 8),
                   "l"(g.blob + (size_t)((blockIdx.x >> 3) * NKB + kb) * B_BYTES) : "memory");
}
__device__ __forceinline__ void load_raw(const CUtensorMap* tmq, uint32_t dst, uint32_t bar, int col, int row) {
    asm volatile("{\n.reg .pred p;\nelect.sync _|p, 0xffffffff;\n"
                 "@p mbarrier.arrive.expect_tx.shared::cta.b64 _, [%1], 14336;\n"
                 "@p cp.async.bulk.tensor.2d.shared::cluster.global.mbarrier::complete_tx::bytes [%0], [%2, {%3, %4}], [%1];\n}"
                 ::"r"(dst), "r"(bar), "l"(tmq), "r"(col), "r"(row) : "memory");
}
__device__ __forceinline__ void wait_flag(const Scratch& g, int kb, unsigned target, unsigned first) {
    asm volatile("{\n.reg .pred p;\n.reg .u32 c, v;\nmov.u32 c, 0;\nmov.u32 v, %2;\n"
                 "FL:\nsub.u32 v, v, %1;\nsetp.ge.s32 p, v, 0;\nvote.sync.all.pred p, p, 0xffffffff;\n@p bra.uni FD;\n"
                 "add.u32 c, c, 1;\nsetp.lt.u32 p, c, 0x100000;\n@p bra.uni FK;\ntrap;\n"
                 "FK:\nld.relaxed.gpu.global.u32 v, [%0];\nbra.uni FL;\nFD:\n}"
                 ::"l"(flag_ptr(g, blockIdx.x >> 3, kb)), "r"(target), "r"(first) : "memory");
}

__device__ __forceinline__ int src_col(int t) { return (t & ~30) | ((t & 6) << 2) | ((t & 24) >> 2); }

__device__ __forceinline__ uint4 dequant8(const int (&q)[8], uint32_t tab, uint32_t sc) {
    uint32_t o[4];
#pragma unroll
    for (int r = 0; r < 4; r++)
        o[r] = mul_bf16x2(__byte_perm(__shfl_sync(~0u, tab, q[2 * r]), __shfl_sync(~0u, tab, q[2 * r + 1]), 0x5410), sc);
    return make_uint4(o[0], o[1], o[2], o[3]);
}
struct Planes { uint32_t lo[4], hi[4]; };
__device__ __forceinline__ uint4 dequant8_prmt(const int (&q)[8], const Planes& p, uint32_t sc) {
    uint32_t o[4];
#pragma unroll
    for (int h = 0; h < 2; h++) {
        const uint32_t c = (q[4 * h] + q[4 * h + 1] * 16) + (q[4 * h + 2] + q[4 * h + 3] * 16) * 256;
        const uint32_t s = c & 0x7777, m = ((c >> 1) & 0x4444) | 0x3210;
        const uint32_t lo = prmt(prmt(p.lo[0], p.lo[1], s), prmt(p.lo[2], p.lo[3], s), m);
        const uint32_t hi = prmt(prmt(p.hi[0], p.hi[1], s), prmt(p.hi[2], p.hi[3], s), m);
        o[2 * h] = mul_bf16x2(prmt(lo, hi, 0x5140), sc);
        o[2 * h + 1] = mul_bf16x2(prmt(lo, hi, 0x7362), sc);
    }
    return make_uint4(o[0], o[1], o[2], o[3]);
}
struct Deq { int q[8]; uint32_t tab, sc, ack, src, dst; };
__device__ __forceinline__ void deq_load(Deq& d, const int* qw) {
    const int* p = (const int*)((const uint8_t*)qw + d.src);
#pragma unroll
    for (int r = 0; r < 8; r++) d.q[r] = ld_code(p + r * F_DIM);
    d.src += BK * F_DIM * 4;
}
__device__ __forceinline__ void deq_prefetch(const Deq& d, const int* qw) {
    const int lane = threadIdx.x & 31;
    asm volatile("{\n.reg .pred p;\nsetp.lt.u32 p, %1, 8;\n@p prefetch.global.L2 [%0];\n}"
                 ::"l"((const uint8_t*)qw + d.src + (lane & 7) * (F_DIM * 4) - src_col(lane) * 4), "r"(lane) : "memory");
}
__device__ __forceinline__ void deq_store(Deq& d, const Scratch& g) {
    const uint4 w = dequant8(d.q, d.tab, d.sc);
    asm volatile("{\n.reg .pred p;\nsetp.eq.u32 p, %6, 0;\nst.global.v4.b32 [%1], {%2, %3, %4, %5};\n@p ld.relaxed.gpu.global.b32 %0, [%1];\n}"
                 : "+r"(d.ack) : "l"(g.blob + d.dst), "r"(w.x), "r"(w.y), "r"(w.z), "r"(w.w), "r"(threadIdx.x & 1) : "memory");
    d.dst += B_BYTES;
}
__device__ __forceinline__ void deq_signal(const Deq& d, const Scratch& g, int piece) {
    const unsigned inc = (threadIdx.x < 32 ? 2u : 1u) + (d.ack & g.zero);
    asm volatile("{\n.reg .pred p;\nelect.sync _|p, 0xffffffff;\n@p red.relaxed.gpu.global.add.u32 [%0], %1;\n}"
                 ::"l"(flag_ptr(g, blockIdx.x >> 3, piece)), "r"(inc) : "memory");
}
__device__ __forceinline__ void deq_step(Deq& d, const Scratch& g, const int* qw, int piece) {
    deq_store(d, g);
    if (piece + 1 < NOWN) deq_load(d, qw);
}

template <int NR> __device__ __forceinline__ uint4 pack8(const float (&a)[NR], int o) {
    return make_uint4(pack_bf16(a[o], a[o + 1]), pack_bf16(a[o + 4], a[o + 5]), pack_bf16(a[o + 8], a[o + 9]), pack_bf16(a[o + 12], a[o + 13]));
}
template <int G0, int NG, int R0, int NR>
__device__ __forceinline__ void store_cols(const float (&a)[NR], const CUtensorMap* tmo, uint32_t stg, int row) {
    const int lane = threadIdx.x & 31;
    const uint32_t p = stg + (lane >> 2) * 64 + (((lane & 3) ^ (lane >> 3)) << 4);
#pragma unroll
    for (int i = 0; i < 2 * NG; i++) sts128(p + i * 512, pack8(a, R0 + 16 * (i >> 1) + 2 * (i & 1)));
    fence_async_smem();
    asm volatile("{\n.reg .pred p;\nelect.sync _|p, 0xffffffff;\n"
                 "@p cp.async.bulk.tensor.3d.global.shared::cta.bulk_group [%0, {0, %2, %3}], [%1];\n"
                 "cp.async.bulk.commit_group;\n}" ::"l"(tmo), "r"(stg), "r"(row), "r"((blockIdx.x >> 3) * 7 + G0) : "memory");
}
template <int G0, int NG, int NR>
__device__ __forceinline__ void store_cols_direct(const float (&a)[NR], uint8_t* out, int row) {
    uint8_t* p = out + (size_t)(row + ((threadIdx.x & 31) >> 2)) * (F_DIM * 2) + (blockIdx.x >> 3) * (BN * 2) + G0 * 64 + (threadIdx.x & 3) * 16;
#pragma unroll
    for (int i = 0; i < 2 * NG; i++) *(uint4*)(p + (i & 1) * 8 * (F_DIM * 2) + (i >> 1) * 64) = pack8(a, 16 * (i >> 1) + 2 * (i & 1));
}

template <int wg>
__device__ __forceinline__ void final_phase(float (&acc0)[112], float (&acc1)[112], const CUtensorMap* tmx, const CUtensorMap* tmo4,
                                            const CUtensorMap* tmo3, uint8_t* out, const Scratch& g, const int warp) {
    constexpr int s0 = wg * 3;
    const int rowg = (blockIdx.x & 7) * BM + wg * 128, roww = rowg + (warp & 3) * 16;
    const bool lead = (warp & 3) == 3;

    wg_wait<0>();
    if ((warp & 3) == 1) {
        arrive_one(BAR_F);
        if (wg == 1) { mbar_wait(BAR_F, 0); fill_b(g, 15); }
    }
    if (wg == 1 && warp == 6) fill_a(tmx, s0 + 2, 12 * BK, rowg + 64, 13 * BK, rowg + 64);
    if (wg == 1) bar_sync<1, 256>();
#pragma unroll
    for (int h = 0; h < 4; h++) {
        if (h & 1) mbar_wait(BAR_B + h * 8, 1);
        else mbar_wait2(BAR_A + (s0 + h / 2) * 8, 0, BAR_B + h * 8, 1);
        wg_fence();
#pragma unroll
        for (int kk = 0; kk < 4; kk++)
            mma(acc0, DESC_A + s0 * (A_SLOT >> 4) + h * 512 + kk * 2, DESC_B + h * (B_BYTES >> 4) + kk * (2 * BN), 1);
        wg_commit();
        if (h == 0 && wg == 0 && lead) fill_a(tmx, s0 + 2, 12 * BK, rowg + 64, 13 * BK, rowg + 64);
    }
    bar_arrive<1 + wg, 256>();
    wg_wait<0>();
    fence_acc(acc0);
    fence_acc(acc1);
    bar_sync<4 + wg, 128>();
    store_cols<4, 3, 64>(acc0, tmo3, SBASE + (s0 + 1) * A_SLOT + (warp & 3) * 3072, roww);
    store_cols<0, 4, 0>(acc0, tmo4, SBASE + s0 * A_SLOT + (warp & 3) * 4096, roww);

    float lo[64], hi[48];
#pragma unroll
    for (int i = 0; i < 64; i++) asm volatile("mov.b32 %0, %1;" : "=f"(lo[i]) : "f"(acc1[i]));
#pragma unroll
    for (int i = 0; i < 48; i++) asm volatile("mov.b32 %0, %1;" : "=f"(hi[i]) : "f"(acc1[64 + i]));
    uint32_t af[64];
    const uint32_t arow = (warp & 3) * 16 + (threadIdx.x & 15);
    const uint32_t abase = SBASE + arow * 128, asw = ((threadIdx.x >> 4) & 1) ^ (arow & 7);
    auto load_frags = [&](int half) {
        mbar_wait(BAR_A + (half ? 6 : s0 + 2) * 8, half ? wg : 0);
#pragma unroll
        for (int i = 8 * half; i < 8 * half + 8; i++)
            asm volatile("ldmatrix.sync.aligned.m8n8.x4.shared.b16 {%0, %1, %2, %3}, [%4];"
                         : "=r"(af[4 * i]), "=r"(af[4 * i + 1]), "=r"(af[4 * i + 2]), "=r"(af[4 * i + 3])
                         : "r"(abase + (half ? 6 : s0 + 2) * A_SLOT + ((i >> 2) & 1) * 8192 + ((asw ^ (2 * (i & 3))) << 4)) : "memory");
    };
    if (wg == 0) {
        load_frags(1);
        bar_sync<4, 128>();
        if (lead) fill_a(tmx, 6, 14 * BK, rowg + 192, 15 * BK, rowg + 192);
    }
    load_frags(0);
#pragma unroll
    for (int part = 0; part < 2; part++) {
        if (part == 0) bar_sync<2 + wg, 256>(); else bar_sync<10 + wg, 256>();
        wg_fence();
#pragma unroll
        for (int i = 0; i < 16; i++) {
            if (i == 8 && part == 0 && wg == 1) { wg_commit(); load_frags(1); wg_fence(); }
            const uint32_t db = DESC_B + (i >> 2) * (B_BYTES >> 4) + (i & 3) * (2 * BN);
            if (part == 0) wgmma_rs_n128(lo, af + 4 * i, desc_b(db));
            else wgmma_rs_n96(hi, af + 4 * i, desc_b(db + 128));
        }
        wg_commit();
        if (part == 0) { if (wg == 0) bar_arrive<3, 256>(); else bar_arrive<10, 256>(); }
        else if (wg == 0) bar_arrive<11, 256>();
        wg_wait<0>();
        if (part == 0) {
            fence_acc(lo);
            bar_sync<4 + wg, 128>();
            store_cols<0, 4, 0>(lo, tmo4, SBASE + (s0 + 2) * A_SLOT + (warp & 3) * 4096, roww + 64);
        } else {
            fence_acc(hi);
            store_cols_direct<4, 3>(hi, out, roww + 64);
        }
    }
    asm volatile("cp.async.bulk.wait_group.read 0;" ::: "memory");
}

__device__ __forceinline__ void helper_role(const CUtensorMap* tmq, const __nv_bfloat16* cb, const __nv_bfloat16* am, const Scratch& g, int warp) {
    constexpr int NP = NKB - NOWN;
    constexpr uint32_t full = BARS, empty = BARS + 96, done = BARS + 120;
    const int j0 = (blockIdx.x - MT * NT) * 4, lane = threadIdx.x & 31;
    if (threadIdx.x == 0) {
        for (int s = 0; s < 12; s++) mbar_init(full + s * 8, 1);
        for (int s = 0; s < 3; s++) { mbar_init(empty + s * 8, 7); mbar_init(done + s * 8, 7); }
        mbar_init_fence();
    }
    __syncthreads();
    auto load_unit = [&](int u) {
        for (int s = 0; s < 4; s++)
            load_raw(tmq, SBASE + ((u % 3) * 4 + s) * RAW_BOX, full + ((u % 3) * 4 + s) * 8, (j0 + (u & 3)) * BN, (NOWN + (u >> 2)) * BK + s * 16);
    };
    if (warp == 7) {
        const long long c0 = clock64();
        while (clock64() - c0 < HELPER_DELAY) __nanosleep(100);
        for (int u = 0; u < 3; u++) load_unit(u);
#pragma unroll 1
        for (int p = 0; p < NP; p++) {
            mbar_wait(done + p * 8, 0);
            asm volatile("fence.acq_rel.gpu;" ::: "memory");
            if (lane < 4) asm volatile("red.relaxed.gpu.global.add.u32 [%0], 64;" ::"l"(flag_ptr(g, j0 + lane, NOWN + p)) : "memory");
        }
    } else {
        const int col = src_col(threadIdx.x);
        const uint32_t tab = ld_u16(cb + (lane & 15));
        uint32_t sc[4];
#pragma unroll
        for (int j = 0; j < 4; j++) sc[j] = ld_u16(am + (j0 + j) * BN + col) * 0x10001u;
#pragma unroll 1
        for (int p = 0; p < NP; p++) {
#pragma unroll
            for (int j = 0; j < 4; j++) {
                const int u = p * 4 + j, slot = u % 3;
                uint8_t* dst = g.blob + (size_t)((j0 + j) * NKB + NOWN + p) * B_BYTES + threadIdx.x * 16;
                int t[8][8];
#pragma unroll
                for (int s = 0; s < 4; s++) {
                    mbar_wait(full + (slot * 4 + s) * 8, (u / 3) & 1);
#pragma unroll
                    for (int i = 0; i < 16; i++) t[2 * s + (i >> 3)][i & 7] = lds32(SBASE + (slot * 4 + s) * RAW_BOX + i * (BN * 4) + col * 4);
                }
                uint4 w[8];
#pragma unroll
                for (int c = 0; c < 8; c++) w[c] = dequant8(t[c], tab, sc[j]);
                arrive_one(empty + slot * 8);
#pragma unroll
                for (int c = 0; c < 8; c++) *(uint4*)(dst + c * (BN * 16)) = w[c];
                if (warp == j && u + 3 < 4 * NP) { mbar_wait(empty + slot * 8, (u / 3) & 1); load_unit(u + 3); }
            }
            __syncwarp();
            arrive_one(done + p * 8);
        }
    }
}

__global__ void __launch_bounds__(256, 1)
nf4_gemm_kernel(const __grid_constant__ CUtensorMap tmx, const __grid_constant__ CUtensorMap tmq,
                const __grid_constant__ CUtensorMap tmo4, const __grid_constant__ CUtensorMap tmo3, uint8_t* __restrict__ out,
                const int* __restrict__ qw, const __nv_bfloat16* __restrict__ cb, const __nv_bfloat16* __restrict__ am, const Scratch g) {
    extern __shared__ __align__(1024) uint8_t smem_raw[];
    const int mi = blockIdx.x & 7, nj = blockIdx.x >> 3, lane = threadIdx.x & 31;
    if (blockIdx.x >= MT * NT) {
        if ((uint32_t)__cvta_generic_to_shared(smem_raw) != SBASE) asm volatile("trap;");
        helper_role(&tmq, cb, am, g, __shfl_sync(~0u, threadIdx.x >> 5, 0));
        return;
    }

    Deq d;
    const int col = src_col(threadIdx.x);
    d.ack = 0;
    d.src = ((BK + mi * 8) * F_DIM + nj * BN + col) * 4;
    d.dst = ((nj * 128 + 8 + mi) * BN + threadIdx.x) * 16;
    constexpr uint32_t raw = SBASE + OFF_B + 2 * B_BYTES;
    const bool worker = __all_sync(~0u, threadIdx.x < 224);
    if (worker) deq_load(d, qw);
    const int warp = __shfl_sync(~0u, threadIdx.x >> 5, 0);
    const int wg = warp >> 2;
    if (worker) {
        d.tab = ld_u16(cb + (lane & 15));
        d.sc = ld_u16(am + nj * BN + col);
        uint32_t cw[8];
        asm volatile("ld.global.v4.b32 {%0, %1, %2, %3}, [%4];" : "=r"(cw[0]), "=r"(cw[1]), "=r"(cw[2]), "=r"(cw[3]) : "l"(cb) : "memory");
        asm volatile("ld.global.v4.b32 {%0, %1, %2, %3}, [%4];" : "=r"(cw[4]), "=r"(cw[5]), "=r"(cw[6]), "=r"(cw[7]) : "l"(cb + 8) : "memory");
        __syncwarp();
        d.sc *= 0x10001u;
        Planes pl;
#pragma unroll
        for (int i = 0; i < 4; i++) { pl.lo[i] = prmt(cw[2 * i], cw[2 * i + 1], 0x6420); pl.hi[i] = prmt(cw[2 * i], cw[2 * i + 1], 0x7531); }
        deq_store(d, g);
        deq_prefetch(d, qw);
        bar_sync<7, 256>();
        int t[8][8];
        auto convert = [&](int c) {
            sts128(SBASE + OFF_B + (c * BN + threadIdx.x) * 16, c == 6 ? dequant8(t[c], d.tab, d.sc) : dequant8_prmt(t[c], pl, d.sc));
        };
#pragma unroll
        for (int s = 0; s < 4; s++) {
            mbar_wait(BAR_R + s * 8, 0);
#pragma unroll
            for (int i = 0; i < 16; i++) t[2 * s + (i >> 3)][i & 7] = lds32(raw + s * RAW_BOX + i * (BN * 4) + col * 4);
            if (s == 1) { deq_signal(d, g, 1); deq_load(d, qw); }
            if (s == 2) deq_prefetch(d, qw);
            if (s > 0) { convert(2 * s - 2); convert(2 * s - 1); }
        }
        convert(6);
        convert(7);
        fence_async_smem();
        if (wg == 0) bar_arrive<8, 256>(); else bar_arrive<9, 256>();
        deq_step(d, g, qw, 2);
        mbar_wait(BAR_A + wg * 24, 0);
        if (wg == 0) bar_sync<9, 256>(); else bar_sync<8, 256>();
    } else {
        if (lane == 0) {
            for (int s = 0; s < 4; s++) mbar_init(BAR_R + s * 8, 1);
            mbar_init(BAR_A, 1);
            mbar_init(BAR_A + 24, 1);
            mbar_init_fence();
        }
        __syncwarp();
        load_raw(&tmq, raw, BAR_R, nj * BN, 0);
        fill_a(&tmx, 0, 0, mi * BM, 0, mi * BM + 64);
        for (int s = 1; s < 4; s++) load_raw(&tmq, raw + s * RAW_BOX, BAR_R + s * 8, nj * BN, s * 16);
        fill_a(&tmx, 3, 0, mi * BM + 128, 0, mi * BM + 192);
        bar_arrive<7, 256>();
        d.ack = ld_relaxed(flag_ptr(g, nj, (lane & 3) ? (lane & 3) : NOWN - 1));
        if (lane == 0) {
            for (int s = 1; s < 7; s++) if (s != 3) mbar_init(BAR_A + s * 8, 1);
            for (int s = 0; s < 4; s++) { mbar_init(BAR_B + s * 8, 1); mbar_init(BAR_E + s * 8, 2); }
            mbar_init(BAR_F, 3);
            mbar_init_fence();
            asm volatile("mbarrier.arrive.shared::cta.b64 _, [%0];" ::"r"(BAR_B) : "memory");
        }
        __syncwarp();
        bar_arrive<9, 256>();
        d.tab = (__shfl_sync(~0u, d.ack, 0) & ~63u) + 64;
        d.sc = 0;
        wait_flag(g, 1, d.tab, __shfl_sync(~0u, d.ack, 1));
        fill_a(&tmx, 1, BK, mi * BM, BK, mi * BM + 64);
        fill_b(g, 1);
        fill_a(&tmx, 4, BK, mi * BM + 128, BK, mi * BM + 192);
        mbar_wait(BAR_A + 24, 0);
        bar_sync<8, 256>();
    }

    float acc0[112], acc1[112];
    const int rowg = mi * BM + wg * 128;
    wg_fence();
#pragma unroll
    for (int kk = 0; kk < 4; kk++) {
        mma(acc0, DESC_A + wg * 3 * (A_SLOT >> 4) + 2 * kk, DESC_B + kk * 2 * BN, kk);
        mma(acc1, DESC_A + wg * 3 * (A_SLOT >> 4) + 512 + 2 * kk, DESC_B + kk * 2 * BN, kk);
    }
    wg_commit();
#pragma unroll 1
    for (int kb = 0; kb < KB1; kb++) {
        if (kb > 0) {
            const int as = wg * 3 + ((0x924924 >> (2 * kb)) & 3);
            mbar_wait2(BAR_A + as * 8, (0xE38 >> kb) & 1, BAR_B + (kb & 3) * 8, (kb >> 2) & 1);
            const uint32_t da = DESC_A + as * (A_SLOT >> 4), db = DESC_B + (kb & 3) * (B_BYTES >> 4);
            if (!worker && kb > 1) d.ack = ld_relaxed(flag_ptr(g, nj, kb + 2 + (kb >= KB1 - 2 ? min(lane, 2) : 0)));
            wg_fence();
#pragma unroll
            for (int i = 0; i < 8; i++) {
                if (i & 1) mma(acc1, da + 512 + (i & 6), db + (i & 6) * BN, 1); else mma(acc0, da + (i & 6), db + (i & 6) * BN, 1);
                if (i == 4) {
                    wg_commit();
                    if (worker && kb + 2 < NOWN) deq_signal(d, g, kb + 2);
                    wg_fence();
                }
            }
            wg_commit();
        }
        wg_wait<2>();
        if (worker) {
            if ((warp & 3) == 2 && kb > 0) {
                const bool tail = kb + 2 >= KB1;
                const int k0 = tail ? 2 * kb - 8 : kb + 2;
                arrive_one(BAR_E + ((kb - 1) & 3) * 8);
                fill_a(&tmx, wg * 3 + ((0x924924 >> (2 * kb - 2)) & 3), k0 * BK, rowg, (tail ? k0 + 1 : k0) * BK, tail ? rowg : rowg + 64);
            }
            if (kb == 0) deq_signal(d, g, 2);
            if (kb + 3 < NOWN) deq_step(d, g, qw, kb + 3);
            if (kb + 5 < NOWN) deq_prefetch(d, qw);
        } else {
            if (kb == 0) for (int w = 0; w < 2; w++) fill_a(&tmx, w * 3 + 2, 2 * BK, mi * BM + w * 128, 2 * BK, mi * BM + w * 128 + 64);
            if (kb == KB1 - 1) { wait_flag(g, 15, d.tab, __shfl_sync(~0u, d.ack, 2)); arrive_one(BAR_F); }
            if (kb < KB1 - 1) {
                if (kb >= 2) mbar_wait(BAR_E + ((kb + 2) & 3) * 8, ((kb - 2) >> 2) & 1);
                wait_flag(g, kb + 2, d.tab, __shfl_sync(~0u, d.ack, kb < 2 ? kb + 2 : 0));
                fill_b(g, kb + 2);
            }
            if (kb >= KB1 - 2) {
                wait_flag(g, kb + 3, d.tab, __shfl_sync(~0u, d.ack, 1));
                mbar_wait(BAR_E + ((kb + 3) & 3) * 8, 0);
                fill_b(g, kb + 3);
            }
            if (kb == 4) fill_a(&tmx, 6, 14 * BK, mi * BM + 64, 15 * BK, mi * BM + 64);
        }
    }
    if (wg == 0) final_phase<0>(acc0, acc1, &tmx, &tmo4, &tmo3, out, g, warp);
    else final_phase<1>(acc0, acc1, &tmx, &tmo4, &tmo3, out, g, warp);
}

__global__ void nf4_fallback_kernel(const __nv_bfloat16* __restrict__ x, const int* __restrict__ qw, const __nv_bfloat16* __restrict__ cb,
                                    const __nv_bfloat16* __restrict__ am, __nv_bfloat16* __restrict__ out) {
    const int f = blockIdx.x * blockDim.x + threadIdx.x, s0 = blockIdx.y * 8;
    const float sc = __bfloat162float(am[f]);
    float acc[8] = {0.f, 0.f, 0.f, 0.f, 0.f, 0.f, 0.f, 0.f};
    for (int k = 0; k < K_DIM; k++) {
        const float w = __bfloat162float(__float2bfloat16(__bfloat162float(cb[qw[(size_t)k * F_DIM + f] & 15]) * sc));
#pragma unroll
        for (int r = 0; r < 8; r++) acc[r] += __bfloat162float(x[(size_t)(s0 + r) * K_DIM + k]) * w;
    }
#pragma unroll
    for (int r = 0; r < 8; r++) out[(size_t)(s0 + r) * F_DIM + f] = __float2bfloat16(acc[r]);
}

typedef CUresult (*EncodeFn)(CUtensorMap*, CUtensorMapDataType, cuuint32_t, void*, const cuuint64_t*, const cuuint64_t*, const cuuint32_t*,
                             const cuuint32_t*, CUtensorMapInterleave, CUtensorMapSwizzle, CUtensorMapL2promotion, CUtensorMapFloatOOBfill);

extern "C" void kernel_launch(void* const* d_in, const int* in_sizes, int n_in, void* d_out, int out_size) {
    static CUtensorMap tmx, tmq, tmo4, tmo3;
    static Scratch g;
    static const void* bound[3] = {nullptr, nullptr, nullptr};
    static bool fused = false;
    const __nv_bfloat16* x = (const __nv_bfloat16*)d_in[0];
    const int* qw = (const int*)d_in[1];
    const __nv_bfloat16* cb = (const __nv_bfloat16*)d_in[2];
    const __nv_bfloat16* am = (const __nv_bfloat16*)d_in[3];
    if (bound[0] != d_in[0] || bound[1] != d_in[1] || bound[2] != d_out) {
        void* fn = nullptr;
        cudaDriverEntryPointQueryResult st;
        cudaGetDriverEntryPoint("cuTensorMapEncodeTiled", &fn, cudaEnableDefault, &st);
        int dev = 0, sms = 0, occ = 0;
        cudaGetDevice(&dev);
        cudaDeviceGetAttribute(&sms, cudaDevAttrMultiProcessorCount, dev);
        fused = fn != nullptr && cudaFuncSetAttribute(nf4_gemm_kernel, cudaFuncAttributeMaxDynamicSharedMemorySize, SMEM_BYTES) == cudaSuccess &&
                cudaOccupancyMaxActiveBlocksPerMultiprocessor(&occ, nf4_gemm_kernel, 256, SMEM_BYTES) == cudaSuccess &&
                sms * occ >= MT * NT + NHELP;
        if (fused) {
            EncodeFn enc = (EncodeFn)fn;
            const cuuint32_t one[3] = {1, 1, 1};
            const cuuint64_t dx[2] = {K_DIM, S_DIM}, sx[1] = {K_DIM * 2}, dq[2] = {F_DIM, K_DIM}, sq[1] = {F_DIM * 4};
            const cuuint64_t dout[3] = {32, S_DIM, F_DIM / 32}, so[2] = {F_DIM * 2, 64};
            const cuuint32_t bx[2] = {64, 64}, bq[2] = {BN, 16}, b4[3] = {32, 16, 4}, b3[3] = {32, 16, 3};
            int err = enc(&tmx, CU_TENSOR_MAP_DATA_TYPE_BFLOAT16, 2, d_in[0], dx, sx, bx, one, CU_TENSOR_MAP_INTERLEAVE_NONE,
                          CU_TENSOR_MAP_SWIZZLE_128B, CU_TENSOR_MAP_L2_PROMOTION_L2_128B, CU_TENSOR_MAP_FLOAT_OOB_FILL_NONE);
            err |= enc(&tmq, CU_TENSOR_MAP_DATA_TYPE_INT32, 2, d_in[1], dq, sq, bq, one, CU_TENSOR_MAP_INTERLEAVE_NONE,
                       CU_TENSOR_MAP_SWIZZLE_NONE, CU_TENSOR_MAP_L2_PROMOTION_NONE, CU_TENSOR_MAP_FLOAT_OOB_FILL_NONE);
            err |= enc(&tmo4, CU_TENSOR_MAP_DATA_TYPE_BFLOAT16, 3, d_out, dout, so, b4, one, CU_TENSOR_MAP_INTERLEAVE_NONE,
                       CU_TENSOR_MAP_SWIZZLE_64B, CU_TENSOR_MAP_L2_PROMOTION_NONE, CU_TENSOR_MAP_FLOAT_OOB_FILL_NONE);
            err |= enc(&tmo3, CU_TENSOR_MAP_DATA_TYPE_BFLOAT16, 3, d_out, dout, so, b3, one, CU_TENSOR_MAP_INTERLEAVE_NONE,
                       CU_TENSOR_MAP_SWIZZLE_64B, CU_TENSOR_MAP_L2_PROMOTION_NONE, CU_TENSOR_MAP_FLOAT_OOB_FILL_NONE);
            err |= cudaGetSymbolAddress((void**)&g.blob, g_wblob) | cudaGetSymbolAddress((void**)&g.flags, g_flags);
            g.zero = 0;
            fused = err == 0;
        }
        (void)cudaGetLastError();
        bound[0] = d_in[0]; bound[1] = d_in[1]; bound[2] = d_out;
    }
    if (fused)
        nf4_gemm_kernel<<<MT * NT + NHELP, 256, SMEM_BYTES, cudaStreamPerThread>>>(tmx, tmq, tmo4, tmo3, (uint8_t*)d_out, qw, cb, am, g);
    else
        nf4_fallback_kernel<<<dim3(F_DIM / 128, S_DIM / 8), 128, 0, cudaStreamPerThread>>>(x, qw, cb, am, (__nv_bfloat16*)d_out);
}
```
